```python
import torch

def _softmax(x, axis=-1):
    return torch.softmax(x, dim=axis)
def _gelu(x):
    return torch.nn.functional.gelu(x, approximate="tanh")
def _silu(x):
    return torch.nn.functional.silu(x)
def _sigmoid(x):
    return torch.sigmoid(x)
def _layernorm(x, axis=-1, eps=1e-5):
    m = x.mean(dim=axis, keepdim=True)
    v = x.var(dim=axis, keepdim=True, unbiased=False)
    return (x - m) / torch.sqrt(v + eps)
def _scatter_add(tgt, idx, src, axis=0):
    return tgt.clone().index_add_(axis, idx, src)
def _segment_sum(src, seg, n):
    out = torch.zeros((n,) + src.shape[1:], dtype=src.dtype)
    return out.index_add_(0, seg, src)
def _pad(x, pw):
    flat = tuple(v for pair in reversed(pw) for v in pair)
    return torch.nn.functional.pad(x, flat)

kernel_name = 'standalone__mha_block_cached__sampling'

def setup_inputs():

    _w = (lambda a: (lambda t: t.to(torch.bfloat16) if t.is_floating_point() else t)(torch.as_tensor(a)))
    B, Sq, D = 16, 1, 1024
    H, Sk, Dh = 32, 2048, 128
    return {
        "x": _w((lambda *s: torch.randn(*s, dtype=torch.bfloat16) * 0.8)(B, Sq, D)),
        "k_cache": _w((lambda *s: torch.randn(*s, dtype=torch.bfloat16) * 0.8)(B, H, Sk, Dh)),
        "v_cache": _w((lambda *s: torch.randn(*s, dtype=torch.bfloat16) * 0.05)(B, H, Sk, Dh)),
        "wq": _w((lambda *s: torch.randn(*s, dtype=torch.bfloat16) * 0.8)(D, H * Dh) * (D ** -0.5)),
        "wo": _w((lambda *s: torch.randn(*s, dtype=torch.bfloat16) * 0.05)(H * Dh, D) * ((H * Dh) ** -0.5)),
    }

def reference(x, k_cache, v_cache, wq, wo):
    B, Sq, D = x.shape
    H, Dh = 32, 128
    q = (lambda x, *d: x.permute(*d))((x @ wq).reshape(B, Sq, H, Dh), 0, 2, 1, 3)
    scores = torch.einsum("bhqd,bhkd->bhqk", q, k_cache) * (Dh ** -0.5)
    p = _softmax(scores, axis=-1)
    o = torch.einsum("bhqk,bhkd->bhqd", p, v_cache)
    return (lambda x, *d: x.permute(*d))(o, 0, 2, 1, 3).reshape(B, Sq, H * Dh) @ wo
```

```cpp
#include <cuda_runtime.h>
#include <cuda_bf16.h>
#include <cuda.h>
#include <stdint.h>

namespace {

constexpr int NB = 16, DM = 1024, NH = 32, SK = 2048, DH = 128;
constexpr int HD = NH * DH;
constexpr int NCTA = 128;
constexpr int TILE = 16384;
#define NSLOT 12
#define INFLIGHT 4
constexpr int NCW = 8;
constexpr int NTHREADS = NCW * 32 + 32;
constexpr int NITEMS = 4 + 4 * 64 + 4;

constexpr int XS_STRIDE = 528;
constexpr int OS_STRIDE = 272;
constexpr int OFF_RING = 0;
constexpr int OFF_XS = OFF_RING + NSLOT * TILE;
constexpr int OFF_SC = OFF_XS + 16 * XS_STRIDE;
constexpr int OFF_OP = OFF_SC + NCW * 256 * 4;
constexpr int OFF_ML = OFF_OP + 2 * NCW * 128 * 4;
constexpr int OFF_QS = OFF_ML + 2 * NCW * 2 * 4;
constexpr int OFF_OS = OFF_QS + 4 * 128 * 2;
constexpr int OFF_BAR = OFF_OS + 16 * OS_STRIDE;
constexpr int OFF_MISC = OFF_BAR + (2 * NSLOT + 1) * 8;
constexpr int SMEM_USED = OFF_MISC + 64;
constexpr int SMEM_BYTES = SMEM_USED + 1024;
static_assert(SMEM_BYTES <= 232448, "too much shared memory");
static_assert(INFLIGHT < NSLOT, "in-flight cap must be below the ring size");

constexpr int PADW = 32;

__device__ float g_qpart[4 * NB * HD];
__device__ __nv_bfloat16 g_o[NB * HD];
__device__ float g_acc[DM * NB];
__device__ unsigned g_ticket;
__device__ unsigned g_qflag[NH * PADW];
__device__ unsigned g_oflag[NH * PADW];
__device__ unsigned g_zflag[4 * PADW];
__device__ unsigned g_colcnt[32 * PADW];

__device__ __forceinline__ uint32_t smem_u32(const void* p) { return (uint32_t)__cvta_generic_to_shared(p); }
__device__ __forceinline__ void mbar_init(uint32_t bar, uint32_t cnt) {
    asm volatile("mbarrier.init.shared::cta.b64 [%0], %1;" ::"r"(bar), "r"(cnt) : "memory");
}
__device__ __forceinline__ void mbar_expect_tx(uint32_t bar, uint32_t bytes) {
    asm volatile("mbarrier.arrive.expect_tx.shared::cta.b64 _, [%0], %1;" ::"r"(bar), "r"(bytes) : "memory");
}
__device__ __forceinline__ void mbar_arrive(uint32_t bar) {
    asm volatile("mbarrier.arrive.shared::cta.b64 _, [%0];" ::"r"(bar) : "memory");
}
__device__ __forceinline__ bool mbar_try(uint32_t bar, uint32_t parity) {
    uint32_t ok;
    asm volatile("{\n.reg .pred p;\nmbarrier.try_wait.parity.shared::cta.b64 p, [%1], %2;\nselp.u32 %0, 1, 0, p;\n}"
                 : "=r"(ok) : "r"(bar), "r"(parity) : "memory");
    return ok;
}
__device__ __forceinline__ void mbar_wait(uint32_t bar, uint32_t parity) {
    for (int i = 0; i < (1 << 22); i++)
        if (mbar_try(bar, parity)) return;
    __trap();
}
__device__ __forceinline__ void bulk_load(uint32_t dst, const void* src, uint32_t bytes, uint32_t bar, uint64_t pol) {
    asm volatile("cp.async.bulk.shared::cluster.global.mbarrier::complete_tx::bytes.L2::cache_hint [%0], [%1], %2, [%3], %4;"
                 ::"r"(dst), "l"(src), "r"(bytes), "r"(bar), "l"(pol) : "memory");
}
__device__ __forceinline__ void bulk_load_plain(uint32_t dst, const void* src, uint32_t bytes, uint32_t bar) {
    asm volatile("cp.async.bulk.shared::cluster.global.mbarrier::complete_tx::bytes [%0], [%1], %2, [%3];"
                 ::"r"(dst), "l"(src), "r"(bytes), "r"(bar) : "memory");
}
__device__ __forceinline__ void tensor_load_2d(uint32_t dst, const CUtensorMap* map, int c0, int c1, uint32_t bar, uint64_t pol) {
    asm volatile("cp.async.bulk.tensor.2d.shared::cluster.global.mbarrier::complete_tx::bytes.L2::cache_hint "
                 "[%0], [%1, {%3, %4}], [%2], %5;"
                 ::"r"(dst), "l"(map), "r"(bar), "r"(c0), "r"(c1), "l"(pol) : "memory");
}
__device__ __forceinline__ void ldsm4(uint32_t (&r)[4], uint32_t addr) {
    asm volatile("ldmatrix.sync.aligned.m8n8.x4.shared.b16 {%0,%1,%2,%3}, [%4];"
                 : "=r"(r[0]), "=r"(r[1]), "=r"(r[2]), "=r"(r[3]) : "r"(addr) : "memory");
}
__device__ __forceinline__ void ldsm4t(uint32_t (&r)[4], uint32_t addr) {
    asm volatile("ldmatrix.sync.aligned.m8n8.x4.trans.shared.b16 {%0,%1,%2,%3}, [%4];"
                 : "=r"(r[0]), "=r"(r[1]), "=r"(r[2]), "=r"(r[3]) : "r"(addr) : "memory");
}
__device__ __forceinline__ void mma16816(float (&c)[4], const uint32_t (&a)[4], uint32_t b0, uint32_t b1) {
    asm volatile("mma.sync.aligned.m16n8k16.row.col.f32.bf16.bf16.f32 {%0,%1,%2,%3}, {%4,%5,%6,%7}, {%8,%9}, {%0,%1,%2,%3};"
                 : "+f"(c[0]), "+f"(c[1]), "+f"(c[2]), "+f"(c[3])
                 : "r"(a[0]), "r"(a[1]), "r"(a[2]), "r"(a[3]), "r"(b0), "r"(b1));
}
__device__ __forceinline__ uint32_t pack_bf16(float lo, float hi) {
    uint32_t r;
    asm("cvt.rn.bf16x2.f32 %0, %1, %2;" : "=r"(r) : "f"(hi), "f"(lo));
    return r;
}
__device__ __forceinline__ float ex2(float x) {
    float r;
    asm("ex2.approx.ftz.f32 %0, %1;" : "=f"(r) : "f"(x));
    return r;
}
__device__ __forceinline__ void consumer_sync() { asm volatile("bar.sync 1, 256;" ::: "memory"); }
__device__ __forceinline__ void red_release(unsigned* p) {
    asm volatile("red.release.gpu.global.add.u32 [%0], 1;" ::"l"(p) : "memory");
}
__device__ __forceinline__ void wait_flag(const unsigned* p, unsigned target) {
    for (int i = 0; i < (1 << 24); i++) {
        unsigned v;
        asm volatile("ld.acquire.gpu.global.u32 %0, [%1];" : "=r"(v) : "l"(p) : "memory");
        if ((int)(v - target) >= 0) return;
    }
    __trap();
}

__global__ void __launch_bounds__(NTHREADS, 1)
mha_block_kernel(const __grid_constant__ CUtensorMap map_wq, const __grid_constant__ CUtensorMap map_wo,
                 const __nv_bfloat16* __restrict__ x, const __nv_bfloat16* __restrict__ kc,
                 const __nv_bfloat16* __restrict__ vc, __nv_bfloat16* __restrict__ out) {
    extern __shared__ uint8_t smem_raw[];
    const uint32_t raw = smem_u32(smem_raw);
    const uint32_t sbase = (raw + 1023u) & ~1023u;
    uint8_t* sm = smem_raw + (sbase - raw);

    const int tid = threadIdx.x, warp = tid >> 5, lane = tid & 31;
    const int h = blockIdx.x & 31, j = blockIdx.x >> 5;
    const uint32_t bar_full = sbase + OFF_BAR, bar_empty = bar_full + NSLOT * 8, bar_x = bar_empty + NSLOT * 8;
    volatile unsigned* misc = reinterpret_cast<volatile unsigned*>(sm + OFF_MISC);

    if (tid == NCW * 32) {
        for (int i = 0; i < NSLOT; i++) { mbar_init(bar_full + i * 8, 1); mbar_init(bar_empty + i * 8, 1); }
        mbar_init(bar_x, 1);
        asm volatile("fence.mbarrier_init.release.cluster;" ::: "memory");
    }
    if (tid < 4) misc[tid] = 0;
    __syncthreads();

    if (warp == NCW) {
        if (lane == 0) mbar_expect_tx(bar_x, 16 * 512);
        __syncwarp();
        uint64_t pol;
        asm volatile("createpolicy.fractional.L2::evict_first.b64 %0, 1.0;" : "=l"(pol));
        if (lane >= 16) {
            const int b = lane - 16;
            bulk_load_plain(sbase + OFF_XS + b * XS_STRIDE, x + b * DM + j * 256, 512, bar_x);
        }
        if (lane == 0) {
            int slot = 0, ph = 0;
            int wslot = 0, wph = 0;
            const char* kbase = reinterpret_cast<const char*>(kc) + (size_t)blockIdx.x * (SK * DH * 2);
            const char* vbase = reinterpret_cast<const char*>(vc) + (size_t)blockIdx.x * (SK * DH * 2);
            for (int i = 0; i < NITEMS; i++) {
                if (i >= INFLIGHT) {
                    mbar_wait(bar_full + wslot * 8, wph);
                    if (++wslot == NSLOT) { wslot = 0; wph ^= 1; }
                }
                if (i >= NSLOT) mbar_wait(bar_empty + slot * 8, ph ^ 1);
                const uint32_t fb = bar_full + slot * 8, dst = sbase + OFF_RING + slot * TILE;
                mbar_expect_tx(fb, TILE);
                if (i < 4) {
                    tensor_load_2d(dst, &map_wq, h * 128 + (i & 1) * 64, j * 256 + (i >> 1) * 128, fb, pol);
                } else if (i < NITEMS - 4) {
                    const int u = i - 4, r = u >> 6, tt = u & 31;
                    const char* src = ((u & 32) ? vbase : kbase) + (size_t)r * ((size_t)NCTA * SK * DH * 2) + tt * TILE;
                    bulk_load(dst, src, TILE, fb, pol);
                } else {
                    tensor_load_2d(dst, &map_wo, j * 256 + (i - (NITEMS - 4)) * 64, h * 128, fb, pol);
                }
                if (++slot == NSLOT) { slot = 0; ph ^= 1; }
            }
        }
        return;
    }

    const int g = lane >> 2, t = lane & 3;
    if (tid == 0) misc[4] = atomicAdd(&g_ticket, 1u) / NCTA;
    if (warp == 1) {
        reinterpret_cast<float4*>(g_acc + (j * 256 + h * 8) * NB)[lane] = make_float4(0.f, 0.f, 0.f, 0.f);
    }

    {
        float acc[2][4] = {};
        const int ch = warp >> 2;
        const uint32_t xa = sbase + OFF_XS + ((lane & 7) + 8 * ((lane >> 3) & 1)) * XS_STRIDE + (lane >> 4) * 16;
        const uint32_t woff = ((lane & 7) + 8 * ((lane >> 3) & 1)) * 128 + (((2 * (warp & 3) + (lane >> 4)) ^ (lane & 7)) * 16);
        mbar_wait(bar_x, 0);
#pragma unroll
        for (int rh = 0; rh < 2; rh++) {
            const int item = rh * 2 + ch;
            mbar_wait(bar_full + item * 8, 0);
            const uint32_t wb = sbase + OFF_RING + item * TILE + woff;
#pragma unroll
            for (int ks = 0; ks < 8; ks++) {
                uint32_t a[4], b[4];
                ldsm4(a, xa + (rh * 8 + ks) * 32);
                ldsm4t(b, wb + ks * 2048);
                mma16816(acc[0], a, b[0], b[1]);
                mma16816(acc[1], a, b[2], b[3]);
            }
        }
        float* qp = g_qpart + (size_t)j * NB * HD + h * 128 + warp * 16 + 2 * t;
#pragma unroll
        for (int nt = 0; nt < 2; nt++) {
            *reinterpret_cast<float2*>(qp + g * HD + nt * 8) = make_float2(acc[nt][0], acc[nt][1]);
            *reinterpret_cast<float2*>(qp + (g + 8) * HD + nt * 8) = make_float2(acc[nt][2], acc[nt][3]);
        }
    }
    consumer_sync();
    const unsigned epoch1 = misc[4] + 1;
    if (tid == 0) {
        for (int i = 0; i < 4; i++) mbar_arrive(bar_empty + i * 8);
        __threadfence();
        red_release(&g_qflag[h * PADW]);
        red_release(&g_zflag[j * PADW]);
        wait_flag(&g_qflag[h * PADW], 4u * epoch1);
    }
    consumer_sync();
    {
        const int r = tid >> 6, d2 = tid & 63;
        const float* qp = g_qpart + (size_t)(j + 4 * r) * HD + h * 128 + 2 * d2;
        float2 s0 = __ldcg(reinterpret_cast<const float2*>(qp));
        float2 s1 = __ldcg(reinterpret_cast<const float2*>(qp + NB * HD));
        float2 s2 = __ldcg(reinterpret_cast<const float2*>(qp + 2 * NB * HD));
        float2 s3 = __ldcg(reinterpret_cast<const float2*>(qp + 3 * NB * HD));
        reinterpret_cast<uint32_t*>(sm + OFF_QS)[tid] =
            pack_bf16((s0.x + s1.x) + (s2.x + s3.x), (s0.y + s1.y) + (s2.y + s3.y));
    }
    consumer_sync();

    const float CS = 0.08838834764831845f * 1.4426950408889634f;
    const bool diag = (t == (g >> 1));
    uint32_t koff[4], voff[4];
    {
        const int r7 = lane & 7;
        const int krow = r7 + 8 * ((lane >> 3) & 1), ky = (lane >> 4) ^ r7;
        const int vrow = r7 + 8 * (lane >> 4), vy = ((lane >> 3) & 1) ^ r7;
#pragma unroll
        for (int i = 0; i < 4; i++) {
            koff[i] = krow * 256 + ((32 * i) ^ (16 * ky));
            voff[i] = vrow * 256 + ((32 * i) ^ (16 * vy));
        }
    }
    float* sc = reinterpret_cast<float*>(sm + OFF_SC) + warp * 256;

#pragma unroll 1
    for (int r = 0; r < 4; r++) {
        uint32_t qf[8][2];
        {
            const uint32_t* qs = reinterpret_cast<const uint32_t*>(sm + OFF_QS) + r * 64;
#pragma unroll
            for (int i = 0; i < 8; i++) {
                qf[i][0] = qs[4 * ((2 * i) ^ g) + t];
                qf[i][1] = qs[4 * ((2 * i + 1) ^ g) + t];
            }
        }
#pragma unroll 1
        for (int tt = 0; tt < 4; tt++) {
            const int item = 4 + r * 64 + tt * 8 + warp;
            const int slot = item % NSLOT;
            mbar_wait(bar_full + slot * 8, (item / NSLOT) & 1);
            const uint32_t tb = sbase + OFF_RING + slot * TILE;
            float c[4][4] = {};
#pragma unroll
            for (int i = 0; i < 8; i++) {
#pragma unroll
                for (int mt = 0; mt < 4; mt++) {
                    uint32_t a[4];
                    ldsm4(a, tb + koff[i & 3] + (i >> 2) * 128 + mt * 4096);
                    mma16816(c[mt], a, qf[i][0], qf[i][1]);
                }
            }
            __syncwarp();
            if (lane == 0) mbar_arrive(bar_empty + slot * 8);
            if (diag) {
#pragma unroll
                for (int mt = 0; mt < 4; mt++) {
                    sc[tt * 64 + mt * 16 + g] = (g & 1) ? c[mt][1] : c[mt][0];
                    sc[tt * 64 + mt * 16 + 8 + g] = (g & 1) ? c[mt][3] : c[mt][2];
                }
            }
        }
        __syncwarp();
        float mw, lw;
        {
            float4 s0 = reinterpret_cast<const float4*>(sc)[lane];
            float4 s1 = reinterpret_cast<const float4*>(sc)[32 + lane];
            mw = fmaxf(fmaxf(fmaxf(s0.x, s0.y), fmaxf(s0.z, s0.w)), fmaxf(fmaxf(s1.x, s1.y), fmaxf(s1.z, s1.w)));
#pragma unroll
            for (int o = 16; o > 0; o >>= 1) mw = fmaxf(mw, __shfl_xor_sync(0xffffffffu, mw, o));
            const float mc = mw * CS;
            s0.x = ex2(fmaf(s0.x, CS, -mc)); s0.y = ex2(fmaf(s0.y, CS, -mc));
            s0.z = ex2(fmaf(s0.z, CS, -mc)); s0.w = ex2(fmaf(s0.w, CS, -mc));
            s1.x = ex2(fmaf(s1.x, CS, -mc)); s1.y = ex2(fmaf(s1.y, CS, -mc));
            s1.z = ex2(fmaf(s1.z, CS, -mc)); s1.w = ex2(fmaf(s1.w, CS, -mc));
            lw = ((s0.x + s0.y) + (s0.z + s0.w)) + ((s1.x + s1.y) + (s1.z + s1.w));
#pragma unroll
            for (int o = 16; o > 0; o >>= 1) lw += __shfl_xor_sync(0xffffffffu, lw, o);
            reinterpret_cast<uint4*>(sc)[lane] =
                make_uint4(pack_bf16(s0.x, 0.f), pack_bf16(0.f, s0.y), pack_bf16(s0.z, 0.f), pack_bf16(0.f, s0.w));
            reinterpret_cast<uint4*>(sc)[32 + lane] =
                make_uint4(pack_bf16(s1.x, 0.f), pack_bf16(0.f, s1.y), pack_bf16(s1.z, 0.f), pack_bf16(0.f, s1.w));
        }
        __syncwarp();
        float o[8][4] = {};
#pragma unroll 1
        for (int tt = 0; tt < 4; tt++) {
            const int item = 4 + r * 64 + 32 + tt * 8 + warp;
            const int slot = item % NSLOT;
            uint32_t pb[4][2];
#pragma unroll
            for (int kt = 0; kt < 4; kt++) {
                const uint32_t* pw = reinterpret_cast<const uint32_t*>(sc) + tt * 64 + kt * 16 + g;
                pb[kt][0] = diag ? pw[0] : 0u;
                pb[kt][1] = diag ? pw[8] : 0u;
            }
            mbar_wait(bar_full + slot * 8, (item / NSLOT) & 1);
            const uint32_t tb = sbase + OFF_RING + slot * TILE;
#pragma unroll
            for (int kt = 0; kt < 4; kt++) {
#pragma unroll
                for (int i = 0; i < 8; i++) {
                    uint32_t a[4];
                    ldsm4t(a, tb + voff[i & 3] + (i >> 2) * 128 + kt * 4096);
                    mma16816(o[i], a, pb[kt][0], pb[kt][1]);
                }
            }
            __syncwarp();
            if (lane == 0) mbar_arrive(bar_empty + slot * 8);
        }
        {
            float r1[16];
#pragma unroll
            for (int xx = 0; xx < 16; xx++) r1[xx] = o[xx >> 1][(xx & 1) * 2] + o[xx >> 1][((xx & 1) ^ 1) * 2 + 1];
#pragma unroll
            for (int xx = 0; xx < 16; xx++)
                if (!(xx & 2)) r1[xx] += __shfl_xor_sync(0xffffffffu, r1[xx ^ 2], 1);
#pragma unroll
            for (int xx = 0; xx < 16; xx++)
                if (!(xx & 6)) r1[xx] += __shfl_xor_sync(0xffffffffu, r1[xx ^ 4], 2);
            float* op = reinterpret_cast<float*>(sm + OFF_OP) + ((r & 1) * NCW + warp) * 128;
            op[8 * (0 ^ (2 * t)) + g] = r1[0];
            op[8 * (1 ^ (2 * t)) + g] = r1[1];
            op[8 * (8 ^ (2 * t)) + g] = r1[8];
            op[8 * (9 ^ (2 * t)) + g] = r1[9];
            float* ml = reinterpret_cast<float*>(sm + OFF_ML) + (r & 1) * NCW * 2;
            if (lane == 0) { ml[warp] = mw; ml[NCW + warp] = lw; }
            __threadfence_block();
            __syncwarp();
            unsigned old = 0;
            if (lane == 0) old = atomicAdd(const_cast<unsigned*>(&misc[r]), 1u);
            old = __shfl_sync(0xffffffffu, old, 0);
            if (old == NCW - 1) {
                __threadfence_block();
                const volatile float* mlv = ml;
                float m = mlv[0];
#pragma unroll
                for (int w = 1; w < NCW; w++) m = fmaxf(m, mlv[w]);
                float L = 0.f;
                float4 a = make_float4(0.f, 0.f, 0.f, 0.f);
                const float4* opb = reinterpret_cast<const float4*>(sm + OFF_OP) + (r & 1) * NCW * 32 + lane;
#pragma unroll
                for (int w = 0; w < NCW; w++) {
                    const float f = ex2((mlv[w] - m) * CS);
                    L = fmaf(f, mlv[NCW + w], L);
                    const float4 v = opb[w * 32];
                    a.x = fmaf(f, v.x, a.x); a.y = fmaf(f, v.y, a.y); a.z = fmaf(f, v.z, a.z); a.w = fmaf(f, v.w, a.w);
                }
                const float inv = 1.0f / L;
                uint2 pk = make_uint2(pack_bf16(a.x * inv, a.y * inv), pack_bf16(a.z * inv, a.w * inv));
                *reinterpret_cast<uint2*>(g_o + (size_t)(j + 4 * r) * HD + h * 128 + lane * 4) = pk;
                __threadfence();
                __syncwarp();
                if (lane == 0) red_release(&g_oflag[h * PADW]);
            }
        }
    }

    if (tid == 0) {
        wait_flag(&g_zflag[j * PADW], 32u * epoch1);
        wait_flag(&g_oflag[h * PADW], 16u * epoch1);
    }
    consumer_sync();
    {
        const int b = tid >> 4, cc = tid & 15;
        const uint4 v = __ldcg(reinterpret_cast<const uint4*>(g_o + (size_t)b * HD + h * 128) + cc);
        const int row = 8 * ((b >> 1) & 1) + 2 * (b >> 2) + (b & 1);
        *reinterpret_cast<uint4*>(sm + OFF_OS + row * OS_STRIDE + cc * 16) = v;
    }
    consumer_sync();
    {
        const int item = NITEMS - 4 + (warp >> 1);
        const int slot = item % NSLOT;
        const uint32_t ob = sbase + OFF_OS + ((lane & 7) + 8 * (lane >> 4)) * OS_STRIDE + ((lane >> 3) & 1) * 16;
        uint32_t bf[8][4];
#pragma unroll
        for (int ks = 0; ks < 8; ks++) ldsm4(bf[ks], ob + ks * 32);
        const int krow = (lane & 7) + 8 * (lane >> 4);
        const uint32_t tb = sbase + OFF_RING + slot * TILE + krow * 128;
        const int c0 = 4 * (warp & 1) + ((lane >> 3) & 1);
        float c[2][2][4] = {};
        mbar_wait(bar_full + slot * 8, (item / NSLOT) & 1);
#pragma unroll
        for (int ks = 0; ks < 8; ks++) {
#pragma unroll
            for (int mt = 0; mt < 2; mt++) {
                uint32_t a[4];
                ldsm4t(a, tb + ks * 2048 + (((c0 + 2 * mt) ^ (lane & 7)) * 16));
                mma16816(c[mt][0], a, bf[ks][0], bf[ks][1]);
                mma16816(c[mt][1], a, bf[ks][2], bf[ks][3]);
            }
        }
        const int col0 = j * 256 + warp * 32;
#pragma unroll
        for (int mt = 0; mt < 2; mt++) {
#pragma unroll
            for (int hf = 0; hf < 2; hf++) {
                float* p = g_acc + (col0 + mt * 16 + hf * 8 + g) * NB + 4 * t;
                asm volatile("red.relaxed.gpu.global.add.v4.f32 [%0], {%1,%2,%3,%4};"
                             ::"l"(p), "f"(c[mt][0][hf * 2]), "f"(c[mt][0][hf * 2 + 1]),
                               "f"(c[mt][1][hf * 2]), "f"(c[mt][1][hf * 2 + 1]) : "memory");
            }
        }
        __threadfence();
        __syncwarp();
        unsigned old = 0;
        if (lane == 0) old = atomicAdd(&g_colcnt[(j * 8 + warp) * PADW], 1u);
        old = __shfl_sync(0xffffffffu, old, 0);
        if (old == 32u * epoch1 - 1u) {
            __threadfence();
            const int cp = lane & 15, bh = lane >> 4;
            const float4* ap = reinterpret_cast<const float4*>(g_acc + (col0 + 2 * cp) * NB + bh * 8);
            const float4 u0 = __ldcg(ap), u1 = __ldcg(ap + 1), v0 = __ldcg(ap + 4), v1 = __ldcg(ap + 5);
            uint32_t* op = reinterpret_cast<uint32_t*>(out + (size_t)(bh * 8) * DM + col0 + 2 * cp);
            op[0 * (DM / 2)] = pack_bf16(u0.x, v0.x);
            op[1 * (DM / 2)] = pack_bf16(u0.y, v0.y);
            op[2 * (DM / 2)] = pack_bf16(u0.z, v0.z);
            op[3 * (DM / 2)] = pack_bf16(u0.w, v0.w);
            op[4 * (DM / 2)] = pack_bf16(u1.x, v1.x);
            op[5 * (DM / 2)] = pack_bf16(u1.y, v1.y);
            op[6 * (DM / 2)] = pack_bf16(u1.z, v1.z);
            op[7 * (DM / 2)] = pack_bf16(u1.w, v1.w);
        }
    }
}

typedef CUresult (*EncodeTiledFn)(CUtensorMap*, CUtensorMapDataType, cuuint32_t, void*, const cuuint64_t*,
                                  const cuuint64_t*, const cuuint32_t*, const cuuint32_t*, CUtensorMapInterleave,
                                  CUtensorMapSwizzle, CUtensorMapL2promotion, CUtensorMapFloatOOBfill);

void make_map(EncodeTiledFn fn, CUtensorMap* m, const void* ptr, uint64_t rows, uint64_t cols) {
    cuuint64_t dims[2] = {cols, rows};
    cuuint64_t strides[1] = {cols * 2};
    cuuint32_t box[2] = {64, 128};
    cuuint32_t estr[2] = {1, 1};
    fn(m, CU_TENSOR_MAP_DATA_TYPE_BFLOAT16, 2, const_cast<void*>(ptr), dims, strides, box, estr,
       CU_TENSOR_MAP_INTERLEAVE_NONE, CU_TENSOR_MAP_SWIZZLE_128B, CU_TENSOR_MAP_L2_PROMOTION_L2_256B,
       CU_TENSOR_MAP_FLOAT_OOB_FILL_NONE);
}

}

extern "C" void kernel_launch(void* const* d_in, const int* in_sizes, int n_in, void* d_out, int out_size) {
    (void)in_sizes; (void)n_in; (void)out_size;
    static EncodeTiledFn encode = nullptr;
    if (!encode) {
        void* fn = nullptr;
        cudaDriverEntryPointQueryResult qr;
        cudaGetDriverEntryPoint("cuTensorMapEncodeTiled", &fn, cudaEnableDefault, &qr);
        encode = reinterpret_cast<EncodeTiledFn>(fn);
        cudaFuncSetAttribute(mha_block_kernel, cudaFuncAttributeMaxDynamicSharedMemorySize, SMEM_BYTES);
    }
    CUtensorMap mq, mo;
    make_map(encode, &mq, d_in[3], DM, HD);
    make_map(encode, &mo, d_in[4], HD, DM);
    mha_block_kernel<<<NCTA, NTHREADS, SMEM_BYTES>>>(
        mq, mo, static_cast<const __nv_bfloat16*>(d_in[0]), static_cast<const __nv_bfloat16*>(d_in[1]),
        static_cast<const __nv_bfloat16*>(d_in[2]), static_cast<__nv_bfloat16*>(d_out));
}
```

```cpp
#include <cuda_runtime.h>
#include <cuda_bf16.h>
#include <cuda.h>
#include <stdint.h>

namespace {

constexpr int NB = 16, DM = 1024, NH = 32, DH = 128;
constexpr int HD = NH * DH;
constexpr int NCTA = 128;
constexpr int TILE = 16384;
constexpr int NSLOT = 12;
constexpr int TPP = 2;
constexpr int NSPLIT = 32 / TPP;
constexpr int PPS = NCTA / NSPLIT;
constexpr int NSTEP = NB * NH / PPS;
constexpr int INFLIGHT = 4;
constexpr int GATHER_LAG = 5;
constexpr int WOCAP = 3;
constexpr int PSTEP = 2;
constexpr int CAP_BASE = 540;
constexpr int CAP_GAIN = 96;
constexpr int CAP_BIAS = 64;
constexpr int CAP_MIN = 2;
constexpr int CAP_MAX = 7;
constexpr int NCW = 8;
constexpr int NGRP = TPP < 4 ? TPP : 4;
constexpr int WPG = NCW / NGRP;
constexpr int MT = 4 / WPG;
constexpr int TPG = TPP / NGRP;
constexpr int SPB = NH / PPS;
constexpr int NTHREADS = NCW * 32 + 128;
constexpr int NITEMS = 4 + NSTEP * 2 * TPP + 4;

constexpr int OS_STRIDE = 272;
constexpr int OS_HEAD = 16 * OS_STRIDE;
constexpr int OFF_RING = 0;
constexpr int OFF_OS = OFF_RING + NSLOT * TILE;
constexpr int OFF_OP = OFF_OS + 4 * OS_HEAD;
constexpr int OFF_ML = OFF_OP + NCW * 128 * 4;
constexpr int OFF_BAR = OFF_ML + 2 * NCW * 2 * 4;
constexpr int OFF_MISC = OFF_BAR + (2 * NSLOT + 3) * 8;
constexpr int SMEM_USED = OFF_MISC + 64;
constexpr int SMEM_BYTES = SMEM_USED + 1024;
static_assert(SMEM_BYTES <= 232448 - 2048, "too much shared memory");
static_assert(NSLOT % NGRP == 0 && INFLIGHT < NSLOT && CAP_MAX < NSLOT && NITEMS % PSTEP == 0, "ring geometry");
static_assert(TPP == 2 || TPP == 4 || TPP == 8, "supported splits");

constexpr int PADW = 32;

__device__ __align__(128) uint4 g_qw[NB * 2 * HD / 4];
__device__ __align__(128) unsigned g_ow[NB * NH * NSPLIT * DH];
__device__ __align__(128) uint4 g_ml[NB * NH * NSPLIT * 2];
__device__ __align__(128) uint4 g_pw[16 * 8 * 8 * 32];
__device__ __align__(128) unsigned g_ticket[NH * PADW];
__device__ __align__(128) unsigned g_prog[PADW];


constexpr float SCALE = 0.08838834764831845f;
constexpr float CS = 1.4426950408889634f;

__device__ __forceinline__ uint32_t smem_u32(const void* p) { return (uint32_t)__cvta_generic_to_shared(p); }
__device__ __forceinline__ void mbar_init(uint32_t bar, uint32_t cnt) {
    asm volatile("mbarrier.init.shared::cta.b64 [%0], %1;" ::"r"(bar), "r"(cnt) : "memory");
}
__device__ __forceinline__ void mbar_expect_tx(uint32_t bar, uint32_t bytes) {
    asm volatile("mbarrier.arrive.expect_tx.shared::cta.b64 _, [%0], %1;" ::"r"(bar), "r"(bytes) : "memory");
}
__device__ __forceinline__ void mbar_arrive(uint32_t bar) {
    asm volatile("mbarrier.arrive.shared::cta.b64 _, [%0];" ::"r"(bar) : "memory");
}
__device__ __forceinline__ void mbar_arrive_n(uint32_t bar, uint32_t n) {
    asm volatile("mbarrier.arrive.shared::cta.b64 _, [%0], %1;" ::"r"(bar), "r"(n) : "memory");
}
__device__ __forceinline__ bool mbar_try(uint32_t bar, uint32_t parity) {
    uint32_t ok;
    asm volatile("{\n.reg .pred p;\nmbarrier.try_wait.parity.shared::cta.b64 p, [%1], %2;\nselp.u32 %0, 1, 0, p;\n}"
                 : "=r"(ok) : "r"(bar), "r"(parity) : "memory");
    return ok;
}
__device__ __forceinline__ void mbar_wait(uint32_t bar, uint32_t parity) {
#pragma unroll 1
    for (int i = 0; i < (1 << 22); i++)
        if (mbar_try(bar, parity)) return;
    __trap();
}
__device__ __forceinline__ void bulk_load(uint32_t dst, const void* src, uint32_t bytes, uint32_t bar, uint64_t pol) {
    asm volatile("cp.async.bulk.shared::cluster.global.mbarrier::complete_tx::bytes.L2::cache_hint [%0], [%1], %2, [%3], %4;"
                 ::"r"(dst), "l"(src), "r"(bytes), "r"(bar), "l"(pol) : "memory");
}
__device__ __forceinline__ void tensor_load_2d(uint32_t dst, const CUtensorMap* map, int c0, int c1, uint32_t bar, uint64_t pol) {
    asm volatile("cp.async.bulk.tensor.2d.shared::cluster.global.mbarrier::complete_tx::bytes.L2::cache_hint "
                 "[%0], [%1, {%3, %4}], [%2], %5;"
                 ::"r"(dst), "l"(map), "r"(bar), "r"(c0), "r"(c1), "l"(pol) : "memory");
}
__device__ __forceinline__ void ldsm4(uint32_t (&r)[4], uint32_t addr) {
    asm volatile("ldmatrix.sync.aligned.m8n8.x4.shared.b16 {%0,%1,%2,%3}, [%4];"
                 : "=r"(r[0]), "=r"(r[1]), "=r"(r[2]), "=r"(r[3]) : "r"(addr) : "memory");
}
__device__ __forceinline__ void ldsm4t(uint32_t (&r)[4], uint32_t addr) {
    asm volatile("ldmatrix.sync.aligned.m8n8.x4.trans.shared.b16 {%0,%1,%2,%3}, [%4];"
                 : "=r"(r[0]), "=r"(r[1]), "=r"(r[2]), "=r"(r[3]) : "r"(addr) : "memory");
}
__device__ __forceinline__ void mma16816(float (&c)[4], const uint32_t (&a)[4], uint32_t b0, uint32_t b1) {
    asm volatile("mma.sync.aligned.m16n8k16.row.col.f32.bf16.bf16.f32 {%0,%1,%2,%3}, {%4,%5,%6,%7}, {%8,%9}, {%0,%1,%2,%3};"
                 : "+f"(c[0]), "+f"(c[1]), "+f"(c[2]), "+f"(c[3])
                 : "r"(a[0]), "r"(a[1]), "r"(a[2]), "r"(a[3]), "r"(b0), "r"(b1));
}
__device__ __forceinline__ uint32_t pack_bf16(float lo, float hi) {
    uint32_t r;
    asm("cvt.rn.bf16x2.f32 %0, %1, %2;" : "=r"(r) : "f"(hi), "f"(lo));
    return r;
}
__device__ __forceinline__ float ex2(float x) {
    float r;
    asm("ex2.approx.ftz.f32 %0, %1;" : "=f"(r) : "f"(x));
    return r;
}
__device__ __forceinline__ unsigned tagged(float v, unsigned t2) { return (__float_as_uint(v) & ~3u) | t2; }
__device__ __forceinline__ float untag(unsigned w) { return __uint_as_float(w & ~3u); }
__device__ __forceinline__ void st_words2(void* p, unsigned a, unsigned b) {
    asm volatile("st.relaxed.gpu.global.v2.u32 [%0], {%1,%2};" ::"l"(p), "r"(a), "r"(b) : "memory");
}
__device__ __forceinline__ unsigned lds_acquire(uint32_t addr) {
    unsigned v;
    asm volatile("ld.acquire.cta.shared::cta.u32 %0, [%1];" : "=r"(v) : "r"(addr) : "memory");
    return v;
}
__device__ __forceinline__ void st_words(void* p, unsigned a, unsigned b, unsigned c, unsigned d) {
    asm volatile("st.relaxed.gpu.global.v4.u32 [%0], {%1,%2,%3,%4};" ::"l"(p), "r"(a), "r"(b), "r"(c), "r"(d) : "memory");
}
template <int W>
__device__ __forceinline__ void ld_words(unsigned (&p)[W], const void* src) {
    if constexpr (W == 4)
        asm volatile("ld.relaxed.gpu.global.v4.u32 {%0,%1,%2,%3}, [%4];"
                     : "=r"(p[0]), "=r"(p[1]), "=r"(p[2]), "=r"(p[3]) : "l"(src) : "memory");
    else
        asm volatile("ld.relaxed.gpu.global.v2.u32 {%0,%1}, [%2];" : "=r"(p[0]), "=r"(p[1]) : "l"(src) : "memory");
}
template <int W>
__device__ __forceinline__ bool words_ok(const unsigned (&p)[W], unsigned t2) {
    unsigned x = p[0] ^ t2;
#pragma unroll
    for (int e = 1; e < W; e++) x |= p[e] ^ t2;
    return (x & 3u) == 0u;
}
__device__ __forceinline__ void st_sum4(void* p, const float4 (&v)[4], unsigned t2) {
    st_words(p, tagged((v[0].x + v[1].x) + (v[2].x + v[3].x), t2), tagged((v[0].y + v[1].y) + (v[2].y + v[3].y), t2),
             tagged((v[0].z + v[1].z) + (v[2].z + v[3].z), t2), tagged((v[0].w + v[1].w) + (v[2].w + v[3].w), t2));
}
__device__ __forceinline__ uint2 merge_row(int pair, int lane, unsigned t2, bool live) {
    unsigned p[NSPLIT][4], ml[2] = {t2, t2};
    const unsigned* src = g_ow + pair * (NSPLIT * DH) + 4 * lane;
    const uint4* mlp = g_ml + (pair * NSPLIT + lane) * 2;
    int it = 0;
#pragma unroll 1
    for (; live; it++) {
        if (it == (1 << 22)) __trap();
        if (lane < NSPLIT) ld_words<2>(ml, mlp);
        live = !__all_sync(0xffffffffu, words_ok<2>(ml, t2));
    }
    float wq[NSPLIT];
#pragma unroll 1
    for (int tries = 0;; it = 0) {
        if (++tries == (1 << 22)) __trap();
        if (it == 0 && lane < NSPLIT) ld_words<2>(ml, mlp);
#pragma unroll
        for (int q = 0; q < NSPLIT; q++) ld_words<4>(p[q], src + q * DH);
        const float m = __uint_as_float(ml[0] & 0xffff0000u);
        float M = m;
#pragma unroll
        for (int of = 1; of < NSPLIT; of *= 2) M = fmaxf(M, __shfl_xor_sync(0xffffffffu, M, of));
        float w = ex2((m - M) * CS), L = w * untag(ml[1]);
#pragma unroll
        for (int of = 1; of < NSPLIT; of *= 2) L += __shfl_xor_sync(0xffffffffu, L, of);
        w = __fdividef(w, L);
#pragma unroll
        for (int q = 0; q < NSPLIT; q++) wq[q] = __shfl_sync(0xffffffffu, w, q);
        unsigned x = (ml[0] ^ t2) | (ml[1] ^ t2);
#pragma unroll
        for (int q = 0; q < NSPLIT; q++)
#pragma unroll
            for (int e = 0; e < 4; e++) x |= (p[q][e] ^= t2);
        if (__all_sync(0xffffffffu, (x & 3u) == 0u)) break;
        __nanosleep(100);
    }
    float o[4] = {0.f, 0.f, 0.f, 0.f};
#pragma unroll
    for (int q = 0; q < NSPLIT; q++)
#pragma unroll
        for (int e = 0; e < 4; e++) o[e] = fmaf(wq[q], __uint_as_float(p[q][e]), o[e]);
    return make_uint2(pack_bf16(o[0], o[1]), pack_bf16(o[2], o[3]));
}

template <int QB>
__device__ __forceinline__ void fetch_q(uint8_t* os, uint32_t ready, int s0, int pair0, int lane, unsigned t2) {
    unsigned p[2 * QB][4];
    bool ok;
    int it = 0;
    do {
        if (++it == (1 << 22)) __trap();
        ok = true;
#pragma unroll
        for (int q = 0; q < 2 * QB; q++) {
            const int pair = min(s0 + (q >> 1), NSTEP - 1) * PPS + pair0;
            ld_words<4>(p[q], reinterpret_cast<const unsigned*>(g_qw) + ((pair >> 5) * 2 + (q & 1)) * HD + (pair & 31) * DH + 4 * lane);
        }
#pragma unroll
        for (int q = 0; q < 2 * QB; q++) ok = ok && words_ok<4>(p[q], t2);
    } while (!__all_sync(0xffffffffu, ok));
#pragma unroll
    for (int q = 0; q < QB; q++) {
        const int s = min(s0 + q, NSTEP - 1);
        *reinterpret_cast<uint2*>(os + (s % SPB) * OS_HEAD + (s / SPB) * OS_STRIDE + lane * 8) =
            make_uint2(pack_bf16(untag(p[2 * q][0]) + untag(p[2 * q + 1][0]), untag(p[2 * q][1]) + untag(p[2 * q + 1][1])),
                       pack_bf16(untag(p[2 * q][2]) + untag(p[2 * q + 1][2]), untag(p[2 * q][3]) + untag(p[2 * q + 1][3])));
    }
    __syncwarp();
    if (lane == 0) asm volatile("st.release.cta.shared::cta.u32 [%0], %1;" ::"r"(ready), "r"(s0 + QB) : "memory");
}

__global__ void __launch_bounds__(NTHREADS, 1)
mha_block_kernel(const __grid_constant__ CUtensorMap map_wq, const __grid_constant__ CUtensorMap map_wo,
                 const __nv_bfloat16* __restrict__ x, const __nv_bfloat16* __restrict__ kc,
                 const __nv_bfloat16* __restrict__ vc, __nv_bfloat16* __restrict__ out) {
    extern __shared__ uint8_t smem_raw[];
    const uint32_t raw = smem_u32(smem_raw);
    const uint32_t sbase = (raw + 1023u) & ~1023u;
    uint8_t* sm = smem_raw + (sbase - raw);

    const int tid = threadIdx.x, warp = tid >> 5, lane = tid & 31;
    const int h = blockIdx.x & 31, j = blockIdx.x >> 5;
    const int hg = h >> 2, cb = (h & 3) * 4 + j;
    const int split = blockIdx.x % NSPLIT, pair0 = blockIdx.x / NSPLIT;
    const uint32_t bar_full = sbase + OFF_BAR, bar_empty = bar_full + NSLOT * 8, bar_os = bar_empty + NSLOT * 8,
                   bar_ml = bar_os + 8, bar_late = bar_ml + 8;
    volatile unsigned* misc = reinterpret_cast<volatile unsigned*>(sm + OFF_MISC);

    uint64_t pol;
    asm volatile("createpolicy.fractional.L2::evict_first.b64 %0, 1.0;" : "=l"(pol));
    if (tid == NCW * 32) {
#pragma unroll
        for (int i = 0; i < 4; i++) mbar_init(bar_full + i * 8, 1);
        asm volatile("fence.mbarrier_init.release.cluster;" ::: "memory");
#pragma unroll
        for (int i = 0; i < 4; i++) {
            mbar_expect_tx(bar_full + i * 8, TILE);
            tensor_load_2d(sbase + OFF_RING + i * TILE, &map_wq, h * 128 + (j & 1) * 64, (j >> 1) * 512 + i * 128,
                           bar_full + i * 8, pol);
        }
#pragma unroll
        for (int i = 4; i < NSLOT; i++) mbar_init(bar_full + i * 8, 1);
#pragma unroll
        for (int i = 0; i < NSLOT; i++) mbar_init(bar_empty + i * 8, WPG);
        mbar_init(bar_os, 2);
        mbar_init(bar_ml, NCW);
        mbar_init(bar_late, 4);
        asm volatile("fence.mbarrier_init.release.cluster;" ::: "memory");
#pragma unroll
        for (int i = 0; i < 8; i++) misc[i] = (i == 6) ? INFLIGHT : 0;
    }
    const int g = lane >> 2, t = lane & 3;
    uint4 xf[4][2];
    uint4* qout = g_qw + ((tid >> 4) * 2 + (j >> 1)) * (HD / 4) + h * 32 + (j & 1) * 16 + (tid & 15);
    if (warp < NCW) {
        st_words(qout, 0u, 0u, 0u, 0u);
#pragma unroll
        for (int I = 0; I < 4; I++) {
#pragma unroll
            for (int hh = 0; hh < 2; hh++)
                asm volatile("ld.global.nc.v4.u32 {%0,%1,%2,%3}, [%4];"
                             : "=r"(xf[I][hh].x), "=r"(xf[I][hh].y), "=r"(xf[I][hh].z), "=r"(xf[I][hh].w)
                             : "l"(x + (g + 8 * hh) * DM + (j >> 1) * 512 + (warp >> 1) * 128 + I * 32 + 8 * t));
        }
    }
    unsigned ticket = 0;
    if (tid == NCW * 32 + 32) ticket = atomicAdd(&g_ticket[h * PADW], 1u);
    __syncwarp();
    if (warp != NCW) asm volatile("bar.sync 8, %0;" ::"n"(NTHREADS) : "memory");

    if (warp == NCW) {
        asm volatile("bar.arrive 8, %0;" ::"n"(NTHREADS) : "memory");
        if (lane == 0) {
            int slot = 4, ph = 0;
            int wi = 0, wslot = 0, wph = 0;
            const char* kbase = reinterpret_cast<const char*>(kc) + (size_t)(pair0 * 32 + split) * TILE;
            const char* vbase = reinterpret_cast<const char*>(vc) + (size_t)(pair0 * 32 + split) * TILE;
#pragma unroll 1
            for (int i = 4; i < NITEMS; i++) {
#pragma unroll 1
                while (i - wi >= (i < NITEMS - 4 ? (int)misc[6] : wi < NITEMS - 4 ? min((int)misc[6], WOCAP) : WOCAP)) {
                    mbar_wait(bar_full + wslot * 8, wph);
                    if (++wslot == NSLOT) { wslot = 0; wph ^= 1; }
                    misc[7] = ++wi;
                    if (wi % PSTEP == 0) asm volatile("red.relaxed.gpu.global.add.u32 [%0], 1;" ::"l"(g_prog) : "memory");
                }
                if (i >= NSLOT) mbar_wait(bar_empty + slot * 8, ph ^ 1);
                const uint32_t fb = bar_full + slot * 8, dst = sbase + OFF_RING + slot * TILE;
                mbar_expect_tx(fb, TILE);
                if (i < NITEMS - 4) {
                    const int u = i - 4;
                    const char* src = ((u & TPP) ? vbase : kbase) +
                                      (size_t)(u / (2 * TPP)) * ((size_t)PPS * 32 * TILE) + (u % TPP) * (NSPLIT * TILE);
                    bulk_load(dst, src, TILE, fb, pol);
                } else {
                    tensor_load_2d(dst, &map_wo, cb * 64, (hg * 4 + i - (NITEMS - 4)) * 128, fb, pol);
                }
                if (++slot == NSLOT) { slot = 0; ph ^= 1; }
            }
            misc[7] = NITEMS;
            asm volatile("red.relaxed.gpu.global.add.u32 [%0], %1;" ::"l"(g_prog), "r"(NITEMS / PSTEP - wi / PSTEP) : "memory");
        }
        return;
    }

    if (warp == NCW + 2) {
        if (lane == 0) {
            unsigned tag = 0;
#pragma unroll 1
            for (int i = 0; i < (1 << 22) && (tag = misc[4]) == 0; i++) __nanosleep(100);
            const unsigned base = (tag - 1u) * (unsigned)(NCTA * (NITEMS / PSTEP));
#pragma unroll 1
            for (int i = 0; i < (1 << 22); i++) {
                const int own = (int)misc[7];
                if (own >= NITEMS) break;
                unsigned v;
                asm volatile("ld.relaxed.gpu.global.u32 %0, [%1];" : "=r"(v) : "l"(g_prog) : "memory");
                const int lag = (int)(v - base) * PSTEP - own * NCTA + CAP_BIAS;
                const int cap = min(max((CAP_BASE + ((CAP_GAIN * lag) >> 7)) >> 7, CAP_MIN), CAP_MAX);
                misc[6] = cap;
                __nanosleep(200);
            }
        }
        return;
    }

    if (warp > NCW) {
        const bool first = warp == NCW + 1;
        unsigned tag = 0;
        if (first) {
            if (lane == 0) { tag = (ticket >> 2) + 1u; misc[4] = tag; }
            tag = __shfl_sync(0xffffffffu, tag, 0);
            asm volatile("bar.arrive 2, 288;" ::: "memory");
        }
        asm volatile("bar.sync 3, 320;" ::: "memory");
        const unsigned t2 = misc[4] % 3u + 1u;
        if (first) {
            fetch_q<1>(sm + OFF_OS, sbase + OFF_MISC + 20, 0, pair0, lane, t2);
#pragma unroll 1
            for (int s0 = 1; s0 < NSTEP; s0 += 8) fetch_q<8>(sm + OFF_OS, sbase + OFF_MISC + 20, s0, pair0, lane, t2);
        }
#pragma unroll 1
        for (int b = 0; b < NB - 1; b++) {
            const int need = 4 + 2 * TPP * ((b * NH + hg * 4) / PPS + 1) + GATHER_LAG;
            int it = 0;
#pragma unroll 1
            for (; it < (1 << 22); it++) {
                if ((int)misc[7] >= need && (int)lds_acquire(sbase + OFF_MISC) >= SPB * (b + 1)) break;
                __nanosleep(500);
            }
            if (it == (1 << 22)) __trap();
#pragma unroll 1
            for (int i = first ? 0 : 2; i < (first ? 2 : 4); i++)
                *reinterpret_cast<uint2*>(sm + OFF_OS + i * OS_HEAD + b * OS_STRIDE + lane * 8) =
                    merge_row(b * NH + hg * 4 + i, lane, t2, false);
        }
        __syncwarp();
        if (lane == 0) mbar_arrive(bar_os);
        if (!first) return;
        const uint4* src = g_pw + (cb * 8 + hg) * 8 * 32 + lane;
        __nv_bfloat16* op = out + (size_t)(8 * (hg & 1) + 4 * (lane & 1)) * DM + cb * 64 + (hg >> 1) * 16 + (lane >> 1);
        __syncwarp();
        asm volatile("bar.sync 1, 160;" ::: "memory");
        unsigned p[8][4];
#pragma unroll 1
        for (int it = 0;; it++) {
            if (it == (1 << 22)) __trap();
            unsigned x = 0;
#pragma unroll
            for (int q = 0; q < 8; q++) ld_words<4>(p[q], src + q * 32);
#pragma unroll
            for (int q = 0; q < 8; q++)
#pragma unroll
                for (int e = 0; e < 4; e++) x |= (p[q][e] ^= t2);
            if (__all_sync(0xffffffffu, (x & 3u) == 0u)) break;
        }
#pragma unroll
        for (int e = 0; e < 4; e++) {
            float a[8];
#pragma unroll
            for (int q = 0; q < 8; q++) a[q] = __uint_as_float(p[q][e]);
            op[e * DM] = __float2bfloat16(((a[0] + a[1]) + (a[2] + a[3])) + ((a[4] + a[5]) + (a[6] + a[7])));
        }
        return;
    }

    {
        float acc[4][4] = {};
        const int s = lane & 7, hf = (lane >> 3) & 1;
        const int krow = 8 * (s >> 1) + 2 * hf + (s & 1);
        const uint32_t wb = sbase + OFF_RING + (warp >> 1) * TILE + krow * 128;
        const int cc = 4 * (warp & 1) + (lane >> 4);
        mbar_wait(bar_full + (warp >> 1) * 8, 0);
#pragma unroll
        for (int ks = 0; ks < 8; ks++) {
            const uint4 u = xf[ks >> 1][0], v = xf[ks >> 1][1];
            const uint32_t a[4] = {(ks & 1) ? u.z : u.x, (ks & 1) ? v.z : v.x, (ks & 1) ? u.w : u.y, (ks & 1) ? v.w : v.y};
            uint32_t b0[4], b2[4];
            const int r7 = (krow + 4 * (ks & 1)) & 7;
            ldsm4t(b0, wb + (ks >> 1) * 4096 + (ks & 1) * 512 + ((cc ^ r7) * 16));
            ldsm4t(b2, wb + (ks >> 1) * 4096 + (ks & 1) * 512 + (((cc + 2) ^ r7) * 16));
            mma16816(acc[0], a, b0[0], b0[1]);
            mma16816(acc[1], a, b0[2], b0[3]);
            mma16816(acc[2], a, b2[0], b2[1]);
            mma16816(acc[3], a, b2[2], b2[3]);
        }
        float* rd = reinterpret_cast<float*>(sm + OFF_OS) + warp * 512;
#pragma unroll
        for (int nt = 0; nt < 4; nt++) {
            const int col = (8 * nt + 2 * t) ^ ((g & 3) * 8);
            *reinterpret_cast<float2*>(rd + g * 32 + col) = make_float2(acc[nt][0], acc[nt][1]);
            *reinterpret_cast<float2*>(rd + (g + 8) * 32 + col) = make_float2(acc[nt][2], acc[nt][3]);
        }
    }
    asm volatile("bar.sync 2, 288;" ::: "memory");
    const unsigned t2 = misc[4] % 3u + 1u;
    if (tid < 4) mbar_arrive_n(bar_empty + tid * 8, WPG);
    {
        const int b = tid >> 4, c4 = tid & 15;
        const float* rd = reinterpret_cast<const float*>(sm + OFF_OS) + (c4 >> 3) * 512 + b * 32 +
                          (((4 * c4) & 31) ^ ((b & 3) * 8));
        float4 v[4];
#pragma unroll
        for (int i = 0; i < 4; i++) v[i] = *reinterpret_cast<const float4*>(rd + i * 1024);
        st_sum4(qout, v, t2);
    }
    __syncwarp();
    asm volatile("bar.arrive 3, 320;" ::: "memory");

    const bool diag = (t == (g >> 1));
    const int grp = warp % NGRP;
    uint32_t koff[4], voff[4];
    {
        const int r7 = lane & 7;
        const int krow = r7 + 8 * ((lane >> 3) & 1), ky = (lane >> 4) ^ r7;
        const int vrow = r7 + 8 * (lane >> 4), vy = ((lane >> 3) & 1) ^ r7;
#pragma unroll
        for (int i = 0; i < 4; i++) {
            koff[i] = sbase + OFF_RING + (warp / NGRP) * (TILE / WPG) + krow * 256 + ((32 * i) ^ (16 * ky));
            voff[i] = sbase + OFF_RING + (warp / NGRP) * (TILE / WPG) + vrow * 256 + ((32 * i) ^ (16 * vy));
        }
    }
    int slot = 4 + grp, ph = 0;
    unsigned* pout = reinterpret_cast<unsigned*>(g_pw + ((cb * 8 + 2 * (warp & 3)) * 8 + hg) * 32) + g * 8 + 2 * t;

#pragma unroll 1
    for (int s = 0; s < NSTEP; s++) {
        {
            unsigned rdy = 0;
#pragma unroll 1
            for (int i = 0; i < (1 << 24); i++) {
                rdy = lds_acquire(sbase + OFF_MISC + 20);
                if ((int)rdy > s) break;
            }
            if ((int)rdy <= s) __trap();
        }
        uint32_t qf[8][2];
        {
            const uint32_t* qs = reinterpret_cast<const uint32_t*>(sm + OFF_OS + (s % SPB) * OS_HEAD + (s / SPB) * OS_STRIDE);
#pragma unroll
            for (int i = 0; i < 8; i++) {
                qf[i][0] = qs[4 * ((2 * i) ^ g) + t];
                qf[i][1] = qs[4 * ((2 * i + 1) ^ g) + t];
            }
        }
        float sc[TPG][MT][2];
        float mw = __uint_as_float(0xff7f0000u), lw = 0.f;
#pragma unroll
        for (int tt = 0; tt < TPG; tt++) {
            mbar_wait(bar_full + slot * 8, ph);
            const uint32_t tb = slot * TILE;
            float c[MT][2][4] = {};
#pragma unroll
            for (int i = 0; i < 8; i++) {
#pragma unroll
                for (int mt = 0; mt < MT; mt++) {
                    uint32_t a[4];
                    ldsm4(a, tb + koff[i & 3] + (i >> 2) * 128 + mt * 4096);
                    mma16816(c[mt][i & 1], a, qf[i][0], qf[i][1]);
                }
            }
            __syncwarp();
            if (lane == 0) mbar_arrive(bar_empty + slot * 8);
            slot += NGRP;
            if (slot >= NSLOT) { slot -= NSLOT; ph ^= 1; }
#pragma unroll
            for (int mt = 0; mt < MT; mt++) {
                const float s0 = (g & 1) ? c[mt][0][1] + c[mt][1][1] : c[mt][0][0] + c[mt][1][0];
                const float s1 = (g & 1) ? c[mt][0][3] + c[mt][1][3] : c[mt][0][2] + c[mt][1][2];
                uint32_t u = pack_bf16(s0, s1);
                u = pack_bf16(__uint_as_float(u << 16) * SCALE, __uint_as_float(u & 0xffff0000u) * SCALE);
                sc[tt][mt][0] = diag ? __uint_as_float(u << 16) : -INFINITY;
                sc[tt][mt][1] = diag ? __uint_as_float(u & 0xffff0000u) : -INFINITY;
                mw = fmaxf(mw, fmaxf(sc[tt][mt][0], sc[tt][mt][1]));
            }
        }
#pragma unroll
        for (int o = 16; o > 0; o >>= 1) mw = fmaxf(mw, __shfl_xor_sync(0xffffffffu, mw, o));
        uint32_t pb[TPG][MT][2];
#pragma unroll
        for (int tt = 0; tt < TPG; tt++)
#pragma unroll
            for (int mt = 0; mt < MT; mt++)
#pragma unroll
                for (int e = 0; e < 2; e++) {
                    const float p = ex2((sc[tt][mt][e] - mw) * CS);
                    lw += p;
                    pb[tt][mt][e] = (g & 1) ? pack_bf16(0.f, p) : pack_bf16(p, 0.f);
                }
#pragma unroll
        for (int o = 16; o > 0; o >>= 1) lw += __shfl_xor_sync(0xffffffffu, lw, o);
        volatile float* ml = reinterpret_cast<volatile float*>(sm + OFF_ML) + (s & 1) * 2 * NCW;
        if (lane == 0) {
            ml[warp] = mw; ml[NCW + warp] = lw;
            mbar_arrive(bar_ml);
        }
        const int prow = (s * PPS + pair0) * NSPLIT + split;
        if (s == NSTEP - 4) {
            if (warp >= 4) {
#pragma unroll
                for (int q = 0; q < 4; q++) st_words2(pout + (q >> 1) * 1024 + (q & 1) * 64, 0u, 0u);
            }
            if (warp < 2) {
                const int pr = prow + (3 - warp) * NCTA;
                st_words(g_ow + pr * DH + 4 * lane, 0u, 0u, 0u, 0u);
                if (lane < 2) st_words(g_ml + pr * 2 + lane, 0u, 0u, 0u, 0u);
            }
        }
        float o[8][4] = {};
        float scale, M, L;
#pragma unroll
        for (int tt = 0; tt < TPG; tt++) {
            if (tt == TPG - 1) {
                mbar_wait(bar_ml, s & 1);
                M = ml[0];
#pragma unroll
                for (int w = 1; w < NCW; w++) M = fmaxf(M, ml[w]);
                L = 0.f;
#pragma unroll
                for (int w = 0; w < NCW; w++) L = fmaf(ex2((ml[w] - M) * CS), ml[NCW + w], L);
                scale = ex2((mw - M) * CS);
            }
            mbar_wait(bar_full + slot * 8, ph);
            const uint32_t tb = slot * TILE;
#pragma unroll
            for (int kt = 0; kt < MT; kt++) {
#pragma unroll
                for (int i = 0; i < 8; i++) {
                    uint32_t a[4];
                    ldsm4t(a, tb + voff[i & 3] + (i >> 2) * 128 + kt * 4096);
                    mma16816(o[i], a, pb[tt][kt][0], pb[tt][kt][1]);
                }
            }
            __syncwarp();
            if (lane == 0) mbar_arrive(bar_empty + slot * 8);
            slot += NGRP;
            if (slot >= NSLOT) { slot -= NSLOT; ph ^= 1; }
        }
        float r1[16];
#pragma unroll
        for (int xx = 0; xx < 16; xx++) r1[xx] = o[xx >> 1][(xx & 1) * 2] + o[xx >> 1][((xx & 1) ^ 1) * 2 + 1];
#pragma unroll
        for (int xx = 0; xx < 16; xx++)
            if (!(xx & 2)) r1[xx] += __shfl_xor_sync(0xffffffffu, r1[xx ^ 2], 1);
#pragma unroll
        for (int xx = 0; xx < 16; xx++)
            if (!(xx & 6)) r1[xx] += __shfl_xor_sync(0xffffffffu, r1[xx ^ 4], 2);
        float* op = reinterpret_cast<float*>(sm + OFF_OP) + warp * 128;
        op[8 * (0 ^ (2 * t)) + g] = r1[0] * scale;
        op[8 * (1 ^ (2 * t)) + g] = r1[1] * scale;
        op[8 * (8 ^ (2 * t)) + g] = r1[8] * scale;
        op[8 * (9 ^ (2 * t)) + g] = r1[9] * scale;
        if (warp != NCW - 1) {
            asm volatile("bar.arrive 5, 256;" ::: "memory");
        } else {
            asm volatile("bar.sync 5, 256;" ::: "memory");
            const float4* opb = reinterpret_cast<const float4*>(sm + OFF_OP) + lane;
            float4 v[NCW];
#pragma unroll
            for (int w = 0; w < NCW; w++) v[w] = opb[w * 32];
#pragma unroll
            for (int st = 1; st < NCW; st *= 2)
#pragma unroll
                for (int w = 0; w < NCW; w += 2 * st) {
                    v[w].x += v[w + st].x; v[w].y += v[w + st].y; v[w].z += v[w + st].z; v[w].w += v[w + st].w;
                }
            st_words(g_ow + prow * DH + 4 * lane, tagged(v[0].x, t2), tagged(v[0].y, t2), tagged(v[0].z, t2), tagged(v[0].w, t2));
            if (lane < 2) st_words(g_ml + prow * 2 + lane, tagged(M, t2), tagged(L, t2), t2, t2);
            if (lane == 0) asm volatile("st.release.cta.shared::cta.u32 [%0], %1;" ::"r"(sbase + OFF_MISC), "r"(s + 1) : "memory");
        }
    }

    constexpr int item0 = NITEMS - 4;
    static_assert(item0 % NSLOT == 8, "end-of-stream slot positions");
    if (warp < 4) {
        if ((NB - 1) * NH + hg * 4 >= (NSTEP - 1) * PPS) mbar_wait(bar_full + 7 * 8, ((item0 - 1) / NSLOT) & 1);
        const uint2 o = merge_row((NB - 1) * NH + hg * 4 + warp, lane, t2, true);
        *reinterpret_cast<uint2*>(sm + OFF_OS + warp * OS_HEAD + (NB - 1) * OS_STRIDE + lane * 8) = o;
        __syncwarp();
        if (lane == 0) mbar_arrive(bar_late);
    } else {
        const uint32_t ob = sbase + OFF_OS + (lane & 7) * OS_STRIDE + (lane >> 3) * 16;
        const uint32_t tb = sbase + OFF_RING + 8 * TILE + ((lane & 7) + 8 * (lane >> 4)) * 128 +
                            (((2 * (warp & 3) + ((lane >> 3) & 1)) ^ (lane & 7)) * 16);
        constexpr uint32_t WPH = (item0 / NSLOT) & 1;
        uint32_t a[4][8][4];
        float c0[4][4] = {}, c1[4][4] = {};
        auto publish = [&](const float (&c)[4][4], unsigned* p) {
            st_words2(p, tagged((c[0][0] + c[1][0]) + (c[2][0] + c[3][0]), t2), tagged((c[0][1] + c[1][1]) + (c[2][1] + c[3][1]), t2));
            st_words2(p + 64, tagged((c[0][2] + c[1][2]) + (c[2][2] + c[3][2]), t2), tagged((c[0][3] + c[1][3]) + (c[2][3] + c[3][3]), t2));
        };
        mbar_wait(bar_os, 0);
#pragma unroll
        for (int i = 0; i < 4; i++) {
            uint32_t bf[4][4];
#pragma unroll
            for (int kp = 0; kp < 4; kp++) ldsm4(bf[kp], ob + i * OS_HEAD + kp * 64);
            mbar_wait(bar_full + (8 + i) * 8, WPH);
#pragma unroll
            for (int ks = 0; ks < 8; ks++) ldsm4t(a[i][ks], tb + i * TILE + ks * 2048);
#pragma unroll
            for (int ks = 0; ks < 8; ks++)
                mma16816(c0[ks & 3], a[i][ks], bf[ks >> 1][(ks & 1) * 2], bf[ks >> 1][(ks & 1) * 2 + 1]);
        }
        publish(c0, pout);
        mbar_wait(bar_late, 0);
        __syncwarp();
        asm volatile("bar.arrive 1, 160;" ::: "memory");
#pragma unroll
        for (int kp = 0; kp < 4; kp++) {
            uint32_t bf[4][4];
#pragma unroll
            for (int i = 0; i < 4; i++) ldsm4(bf[i], ob + 8 * OS_STRIDE + i * OS_HEAD + kp * 64);
#pragma unroll
            for (int i = 0; i < 4; i++) mma16816(c1[i], a[i][2 * kp], bf[i][0], bf[i][1]);
#pragma unroll
            for (int i = 0; i < 4; i++) mma16816(c1[i], a[i][2 * kp + 1], bf[i][2], bf[i][3]);
        }
        publish(c1, pout + 1024);
    }
}

__device__ float g_fq[NB * HD], g_fo[NB * HD];
__device__ __forceinline__ float bf16_round(float v) { return __bfloat162float(__float2bfloat16(v)); }
__global__ void fb_proj_q(const __nv_bfloat16* __restrict__ x, const __nv_bfloat16* __restrict__ wq) {
    const int n = blockIdx.x * blockDim.x + threadIdx.x, b = blockIdx.y;
    float a = 0.f;
    for (int k = 0; k < DM; k++) a = fmaf(__bfloat162float(x[b * DM + k]), __bfloat162float(wq[(size_t)k * HD + n]), a);
    g_fq[b * HD + n] = bf16_round(a);
}
__global__ void fb_attn(const __nv_bfloat16* __restrict__ kc, const __nv_bfloat16* __restrict__ vc) {
    __shared__ float s[2048], red[128];
    const int p = blockIdx.x, tid = threadIdx.x;
    const float* q = g_fq + p * DH;
    float m = -INFINITY, l = 0.f;
    for (int k = tid; k < 2048; k += 128) {
        float a = 0.f;
        for (int d = 0; d < DH; d++) a = fmaf(q[d], __bfloat162float(kc[((size_t)p * 2048 + k) * DH + d]), a);
        s[k] = bf16_round(bf16_round(a) * SCALE);
        m = fmaxf(m, s[k]);
    }
    red[tid] = m;
    __syncthreads();
    for (int i = 0; i < 128; i++) m = fmaxf(m, red[i]);
    __syncthreads();
    for (int k = tid; k < 2048; k += 128) l += (s[k] = expf(s[k] - m));
    red[tid] = l;
    __syncthreads();
    l = 0.f;
    for (int i = 0; i < 128; i++) l += red[i];
    float a = 0.f;
    for (int k = 0; k < 2048; k++) a = fmaf(bf16_round(s[k] / l), __bfloat162float(vc[((size_t)p * 2048 + k) * DH + tid]), a);
    g_fo[p * DH + tid] = bf16_round(a);
}
__global__ void fb_proj_o(const __nv_bfloat16* __restrict__ wo, __nv_bfloat16* __restrict__ out) {
    const int n = blockIdx.x * blockDim.x + threadIdx.x, b = blockIdx.y;
    float a = 0.f;
    for (int k = 0; k < HD; k++) a = fmaf(g_fo[b * HD + k], __bfloat162float(wo[(size_t)k * DM + n]), a);
    out[b * DM + n] = __float2bfloat16(a);
}

typedef CUresult (*EncodeTiledFn)(CUtensorMap*, CUtensorMapDataType, cuuint32_t, void*, const cuuint64_t*,
                                  const cuuint64_t*, const cuuint32_t*, const cuuint32_t*, CUtensorMapInterleave,
                                  CUtensorMapSwizzle, CUtensorMapL2promotion, CUtensorMapFloatOOBfill);

void make_map(EncodeTiledFn fn, CUtensorMap* m, const void* ptr, uint64_t rows, uint64_t cols) {
    cuuint64_t dims[2] = {cols, rows};
    cuuint64_t strides[1] = {cols * 2};
    cuuint32_t box[2] = {64, 128};
    cuuint32_t estr[2] = {1, 1};
    fn(m, CU_TENSOR_MAP_DATA_TYPE_BFLOAT16, 2, const_cast<void*>(ptr), dims, strides, box, estr,
       CU_TENSOR_MAP_INTERLEAVE_NONE, CU_TENSOR_MAP_SWIZZLE_128B, CU_TENSOR_MAP_L2_PROMOTION_L2_128B,
       CU_TENSOR_MAP_FLOAT_OOB_FILL_NONE);
}

}

extern "C" void kernel_launch(void* const* d_in, const int* in_sizes, int n_in, void* d_out, int out_size) {
    (void)in_sizes; (void)n_in; (void)out_size;
    const __nv_bfloat16* x = static_cast<const __nv_bfloat16*>(d_in[0]);
    const __nv_bfloat16* kc = static_cast<const __nv_bfloat16*>(d_in[1]);
    const __nv_bfloat16* vc = static_cast<const __nv_bfloat16*>(d_in[2]);
    __nv_bfloat16* out = static_cast<__nv_bfloat16*>(d_out);
    static EncodeTiledFn encode = nullptr;
    static int resident = -1;
    if (resident < 0) {
        void* fn = nullptr;
        cudaDriverEntryPointQueryResult qr;
        cudaGetDriverEntryPoint("cuTensorMapEncodeTiled", &fn, cudaEnableDefault, &qr);
        encode = reinterpret_cast<EncodeTiledFn>(fn);
        cudaFuncSetAttribute(mha_block_kernel, cudaFuncAttributeMaxDynamicSharedMemorySize, SMEM_BYTES);
        int dev = 0, sms = 0, per_sm = 0;
        cudaGetDevice(&dev);
        cudaDeviceGetAttribute(&sms, cudaDevAttrMultiProcessorCount, dev);
        cudaOccupancyMaxActiveBlocksPerMultiprocessor(&per_sm, mha_block_kernel, NTHREADS, SMEM_BYTES);
        resident = encode ? sms * per_sm : 0;
    }
    if (resident < NCTA) {
        fb_proj_q<<<dim3(HD / 128, NB), 128>>>(x, static_cast<const __nv_bfloat16*>(d_in[3]));
        fb_attn<<<NB * NH, 128>>>(kc, vc);
        fb_proj_o<<<dim3(DM / 128, NB), 128>>>(static_cast<const __nv_bfloat16*>(d_in[4]), out);
        return;
    }
    CUtensorMap mq, mo;
    make_map(encode, &mq, d_in[3], DM, HD);
    make_map(encode, &mo, d_in[4], HD, DM);
    cudaLaunchConfig_t cfg = {};
    cfg.gridDim = dim3(NCTA);
    cfg.blockDim = dim3(NTHREADS);
    cfg.dynamicSmemBytes = SMEM_BYTES;
    cfg.stream = cudaStreamPerThread;
    cudaLaunchAttribute at[1];
    at[0].id = cudaLaunchAttributeCooperative;
    at[0].val.cooperative = 1;
    cfg.attrs = at;
    cfg.numAttrs = 1;
    cudaLaunchKernelEx(&cfg, mha_block_kernel, mq, mo, x, kc, vc, out);
}
```
